```python
import torch

def _softmax(x, axis=-1):
    return torch.softmax(x, dim=axis)
def _gelu(x):
    return torch.nn.functional.gelu(x, approximate="tanh")
def _silu(x):
    return torch.nn.functional.silu(x)
def _sigmoid(x):
    return torch.sigmoid(x)
def _layernorm(x, axis=-1, eps=1e-5):
    m = x.mean(dim=axis, keepdim=True)
    v = x.var(dim=axis, keepdim=True, unbiased=False)
    return (x - m) / torch.sqrt(v + eps)
def _scatter_add(tgt, idx, src, axis=0):
    return tgt.clone().index_add_(axis, idx, src)
def _segment_sum(src, seg, n):
    out = torch.zeros((n,) + src.shape[1:], dtype=src.dtype)
    return out.index_add_(0, seg, src)
def _pad(x, pw):
    flat = tuple(v for pair in reversed(pw) for v in pair)
    return torch.nn.functional.pad(x, flat)

kernel_name = 'concat_heads__gqa_block_cached__gqa_block_cached__near_ridge'

def setup_inputs():

    _w = (lambda a: (lambda t: t.to(torch.bfloat16) if t.is_floating_point() else t)(torch.as_tensor(a)))
    def _A_setup():
        B, Sq, D = 16, 48, 640
        Hq, Hkv, Sk, Dh = 32, 32, 48, 192
        assert Hq % Hkv == 0, (Hq, Hkv)
        return {
            "x": _w((lambda *s: torch.randn(*s, dtype=torch.bfloat16) * 0.8)(B, Sq, D)),
            "k_cache": _w((lambda *s: torch.randn(*s, dtype=torch.bfloat16) * 0.8)(B, Hkv, Sk, Dh)),
            "v_cache": _w((lambda *s: torch.randn(*s, dtype=torch.bfloat16) * 0.05)(B, Hkv, Sk, Dh)),
            "wq": _w((lambda *s: torch.randn(*s, dtype=torch.bfloat16) * 0.8)(D, Hq * Dh) * (D ** -0.5)),
            "wo": _w((lambda *s: torch.randn(*s, dtype=torch.bfloat16) * 0.05)(Hq * Dh, D) * ((Hq * Dh) ** -0.5)),
        }
    _A_in = _A_setup()

    def _B_setup():
        B, Sq, D = 16, 48, 640
        Hq, Hkv, Sk, Dh = 32, 32, 48, 192
        assert Hq % Hkv == 0, (Hq, Hkv)
        return {
            "x": _w((lambda *s: torch.randn(*s, dtype=torch.bfloat16) * 0.8)(B, Sq, D)),
            "k_cache": _w((lambda *s: torch.randn(*s, dtype=torch.bfloat16) * 0.8)(B, Hkv, Sk, Dh)),
            "v_cache": _w((lambda *s: torch.randn(*s, dtype=torch.bfloat16) * 0.05)(B, Hkv, Sk, Dh)),
            "wq": _w((lambda *s: torch.randn(*s, dtype=torch.bfloat16) * 0.8)(D, Hq * Dh) * (D ** -0.5)),
            "wo": _w((lambda *s: torch.randn(*s, dtype=torch.bfloat16) * 0.05)(Hq * Dh, D) * ((Hq * Dh) ** -0.5)),
        }
    _B_in = _B_setup()

    return {
        "A_x": _A_in["x"],
        "A_k_cache": _A_in["k_cache"],
        "A_v_cache": _A_in["v_cache"],
        "A_wq": _A_in["wq"],
        "A_wo": _A_in["wo"],
        "B_x": _B_in["x"],
        "B_k_cache": _B_in["k_cache"],
        "B_v_cache": _B_in["v_cache"],
        "B_wq": _B_in["wq"],
        "B_wo": _B_in["wo"],
    }

def reference(A_x, A_k_cache, A_v_cache, A_wq, A_wo, B_x, B_k_cache, B_v_cache, B_wq, B_wo):
    def _A_ref(x, k_cache, v_cache, wq, wo):
        B, Sq, D = x.shape
        Hq, Dh = 32, 192
        Hkv = k_cache.shape[1]
        rep = Hq // Hkv
        q = (lambda x, *d: x.permute(*d))((x @ wq).reshape(B, Sq, Hq, Dh), 0, 2, 1, 3)
        k = (lambda x, n, axis: torch.repeat_interleave(x, n, dim=axis))(k_cache, rep, axis=1)
        v = (lambda x, n, axis: torch.repeat_interleave(x, n, dim=axis))(v_cache, rep, axis=1)
        scores = torch.einsum("bhqd,bhkd->bhqk", q, k) * (Dh ** -0.5)
        p = _softmax(scores, axis=-1)
        o = torch.einsum("bhqk,bhkd->bhqd", p, v)
        return (lambda x, *d: x.permute(*d))(o, 0, 2, 1, 3).reshape(B, Sq, Hq * Dh) @ wo

    def _B_ref(x, k_cache, v_cache, wq, wo):
        B, Sq, D = x.shape
        Hq, Dh = 32, 192
        Hkv = k_cache.shape[1]
        rep = Hq // Hkv
        q = (lambda x, *d: x.permute(*d))((x @ wq).reshape(B, Sq, Hq, Dh), 0, 2, 1, 3)
        k = (lambda x, n, axis: torch.repeat_interleave(x, n, dim=axis))(k_cache, rep, axis=1)
        v = (lambda x, n, axis: torch.repeat_interleave(x, n, dim=axis))(v_cache, rep, axis=1)
        scores = torch.einsum("bhqd,bhkd->bhqk", q, k) * (Dh ** -0.5)
        p = _softmax(scores, axis=-1)
        o = torch.einsum("bhqk,bhkd->bhqd", p, v)
        return (lambda x, *d: x.permute(*d))(o, 0, 2, 1, 3).reshape(B, Sq, Hq * Dh) @ wo

    a = _A_ref(A_x, A_k_cache, A_v_cache, A_wq, A_wo)
    b = _B_ref(B_x, B_k_cache, B_v_cache, B_wq, B_wo)
    return torch.concatenate([a, b], axis=-1)
```

```cpp
#include <cuda_runtime.h>
#include <cuda_bf16.h>
#include <cuda.h>
#include <stdint.h>

namespace {

constexpr int NSLOT = 9;
constexpr int SLOT = 24576;
constexpr int SMEM_BYTES = NSLOT * SLOT + 1024 + 1024 + 6144;
constexpr uint32_t SPIN_LIMIT = 1u << 26;

#define KE 1
constexpr int tile_kind(int t) {
  return t < 20 ? (t & 1) : t < 23 ? 2 : t < 43 ? ((t - 23) & 1) : t < 49 ? 2 : t < 49 + 2 * KE ? 1 : t < 52 + 2 * KE ? 2 : 1;
}
constexpr int tile_slot(int t) {
  const int r7[7] = {4, 5, 6, 7, 8, 0, 3};
  return t < 49 ? t % 9 : r7[(t - 49) % 7];
}
constexpr uint64_t next_kinds(int t0, int n) {
  uint64_t m = 0;
  for (int t = t0; t < t0 + n; t++) {
    int nk = 3;
    for (int k = 71; k > t; k--)
      if (tile_slot(k) == tile_slot(t)) nk = tile_kind(k);
    m |= (uint64_t)nk << (2 * (t - t0));
  }
  return m;
}
constexpr uint64_t NK_A = next_kinds(0, 23), NK_B = next_kinds(23, 23), NK_C = next_kinds(46, 26);
#define NEXT9(s) ((s) == 8 ? 0 : (s) + 1)
#define NEXT7(s) ((s) == 8 ? 0 : (s) == 0 ? 3 : (s) + 1)

struct Params {
  CUtensorMap x[2], wq[2], k[2], v[2], wo[2], out;
  const uint8_t* kp[2];
  const uint8_t* vp[2];
};

constexpr int NCTA = 140;
__device__ unsigned int g_claim[9 * 32];
__device__ unsigned int g_done[8 * 32];
#define FST(r, i) do { } while (0)
#define GSTAMP(i) do { } while (0)
#define STAMP(i) do { } while (0)

__device__ __forceinline__ uint32_t smem_u32(const void* p) { return (uint32_t)__cvta_generic_to_shared(p); }
__device__ __forceinline__ void mbar_init(uint32_t a, uint32_t c) {
  asm volatile("mbarrier.init.shared::cta.b64 [%0], %1;" ::"r"(a), "r"(c) : "memory");
}
__device__ __forceinline__ void mbar_expect_tx(uint32_t a, uint32_t b) {
  asm volatile("mbarrier.arrive.expect_tx.shared::cta.b64 _, [%0], %1;" ::"r"(a), "r"(b) : "memory");
}
__device__ __forceinline__ uint32_t mbar_try(uint32_t a, uint32_t p) {
  uint32_t ok;
  asm volatile("{\n.reg .pred p;\nmbarrier.try_wait.parity.shared::cta.b64 p, [%1], %2;\nselp.u32 %0, 1, 0, p;\n}\n"
               : "=r"(ok) : "r"(a), "r"(p) : "memory");
  return ok;
}
__device__ __forceinline__ uint32_t mbar_test(uint32_t a, uint32_t p) {
  uint32_t ok;
  asm volatile("{\n.reg .pred p;\nmbarrier.test_wait.parity.shared::cta.b64 p, [%1], %2;\nselp.u32 %0, 1, 0, p;\n}\n"
               : "=r"(ok) : "r"(a), "r"(p) : "memory");
  return ok;
}
__device__ __forceinline__ uint32_t clk32() {
  uint32_t c;
  asm volatile("mov.u32 %0, %%clock;" : "=r"(c));
  return c;
}
#define EXPIRED() (clk32() - t_start > SPIN_LIMIT)
__device__ __forceinline__ void mbar_wait_b(uint32_t a, uint32_t p, uint32_t t_start) {
  if (mbar_try(a, p)) return;
  while (!mbar_try(a, p)) {
    if (EXPIRED()) break;
  }
}
#define mbar_wait(a, p) mbar_wait_b(a, p, t_start)
__device__ __forceinline__ uint32_t mapa(uint32_t a, uint32_t cta) {
  uint32_t r;
  asm volatile("mapa.shared::cluster.u32 %0, %1, %2;" : "=r"(r) : "r"(a), "r"(cta));
  return r;
}
__device__ __forceinline__ void mbar_arrive_cluster(uint32_t remote) {
  asm volatile("mbarrier.arrive.shared::cluster.b64 _, [%0];" ::"r"(remote) : "memory");
}
__device__ __forceinline__ void mbar_arrive_cluster_n(uint32_t remote, uint32_t n) {
  asm volatile("mbarrier.arrive.shared::cluster.b64 _, [%0], %1;" ::"r"(remote), "r"(n) : "memory");
}
__device__ __forceinline__ void mbar_arrive_local(uint32_t a) {
  asm volatile("mbarrier.arrive.shared::cta.b64 _, [%0];" ::"r"(a) : "memory");
}
__device__ __forceinline__ void tma2d(uint32_t dst, const CUtensorMap* m, uint32_t bar, int c0, int c1) {
  asm volatile(
      "cp.async.bulk.tensor.2d.shared::cluster.global.mbarrier::complete_tx::bytes [%0], [%1, {%3, %4}], [%2];"
      ::"r"(dst), "l"((uint64_t)m), "r"(bar), "r"(c0), "r"(c1) : "memory");
}
__device__ __forceinline__ void tma2d_mc(uint32_t dst, const CUtensorMap* m, uint32_t bar, int c0, int c1, uint16_t mask) {
  asm volatile(
      "cp.async.bulk.tensor.2d.shared::cluster.global.mbarrier::complete_tx::bytes.multicast::cluster [%0], [%1, {%3, %4}], [%2], %5;"
      ::"r"(dst), "l"((uint64_t)m), "r"(bar), "r"(c0), "r"(c1), "h"(mask) : "memory");
}
__device__ __forceinline__ void tma3d_mc(uint32_t dst, const CUtensorMap* m, uint32_t bar, int c0, int c1, int c2, uint16_t mask) {
  asm volatile(
      "cp.async.bulk.tensor.3d.shared::cluster.global.mbarrier::complete_tx::bytes.multicast::cluster [%0], [%1, {%3, %4, %5}], [%2], %6;"
      ::"r"(dst), "l"((uint64_t)m), "r"(bar), "r"(c0), "r"(c1), "r"(c2), "h"(mask) : "memory");
}
__device__ __forceinline__ void tma3d(uint32_t dst, const CUtensorMap* m, uint32_t bar, int c0, int c1, int c2) {
  asm volatile(
      "cp.async.bulk.tensor.3d.shared::cluster.global.mbarrier::complete_tx::bytes [%0], [%1, {%3, %4, %5}], [%2];"
      ::"r"(dst), "l"((uint64_t)m), "r"(bar), "r"(c0), "r"(c1), "r"(c2) : "memory");
}
__device__ __forceinline__ void tma4d(uint32_t dst, const CUtensorMap* m, uint32_t bar, int c0, int c1, int c2, int c3) {
  asm volatile(
      "cp.async.bulk.tensor.4d.shared::cluster.global.mbarrier::complete_tx::bytes [%0], [%1, {%3, %4, %5, %6}], [%2];"
      ::"r"(dst), "l"((uint64_t)m), "r"(bar), "r"(c0), "r"(c1), "r"(c2), "r"(c3) : "memory");
}
__device__ __forceinline__ void tma_red_add(const CUtensorMap* m, uint32_t src, int c0, int c1) {
  asm volatile("cp.reduce.async.bulk.tensor.2d.global.shared::cta.add.tile.bulk_group [%0, {%2, %3}], [%1];"
               ::"l"((uint64_t)m), "r"(src), "r"(c0), "r"(c1) : "memory");
}
__device__ __forceinline__ void st_async4(uint32_t addr, uint32_t a, uint32_t b, uint32_t c, uint32_t d, uint32_t bar) {
  asm volatile("st.async.weak.shared::cluster.mbarrier::complete_tx::bytes.v4.b32 [%0], {%1, %2, %3, %4}, [%5];"
               ::"r"(addr), "r"(a), "r"(b), "r"(c), "r"(d), "r"(bar) : "memory");
}
__device__ __forceinline__ void stsm4(uint32_t addr, uint32_t r0, uint32_t r1, uint32_t r2, uint32_t r3) {
  asm volatile("stmatrix.sync.aligned.m8n8.x4.shared.b16 [%0], {%1, %2, %3, %4};"
               ::"r"(addr), "r"(r0), "r"(r1), "r"(r2), "r"(r3) : "memory");
}
__device__ __forceinline__ void pf_map(const CUtensorMap* m) {
  asm volatile("prefetch.tensormap [%0];" ::"l"((uint64_t)m) : "memory");
}
__device__ __forceinline__ void wg_fence() { asm volatile("wgmma.fence.sync.aligned;" ::: "memory"); }
__device__ __forceinline__ void wg_commit() { asm volatile("wgmma.commit_group.sync.aligned;" ::: "memory"); }
template <int N> __device__ __forceinline__ void wg_wait() {
  asm volatile("wgmma.wait_group.sync.aligned %0;" ::"n"(N) : "memory");
}
__device__ __forceinline__ uint64_t mk_desc(uint32_t lo, uint32_t hi) {
  uint64_t d;
  asm("mov.b64 %0, {%1, %2};" : "=l"(d) : "r"(lo), "r"(hi));
  return d;
}
__device__ __forceinline__ uint32_t pack_bf16(float lo, float hi) {
  uint32_t r;
  asm("cvt.rn.bf16x2.f32 %0, %1, %2;" : "=r"(r) : "f"(hi), "f"(lo));
  return r;
}
__device__ __forceinline__ uint32_t pack_bf16v(float lo, float hi) {
  uint32_t r;
  asm volatile("cvt.rn.bf16x2.f32 %0, %1, %2;" : "=r"(r) : "f"(hi), "f"(lo));
  return r;
}
__device__ __forceinline__ float ex2(float x) {
  float r;
  asm("ex2.approx.ftz.f32 %0, %1;" : "=f"(r) : "f"(x));
  return r;
}
__device__ __forceinline__ float rcp(float x) {
  float r;
  asm("rcp.approx.ftz.f32 %0, %1;" : "=f"(r) : "f"(x));
  return r;
}
__device__ __forceinline__ unsigned ld_acquire(const unsigned* p) {
  unsigned v;
  asm volatile("ld.acquire.gpu.global.u32 %0, [%1];" : "=r"(v) : "l"(p) : "memory");
  return v;
}
template <int N> __device__ __forceinline__ void reg_fence(float (&d)[N]) {
#pragma unroll
  for (int i = 0; i < N; i++) asm volatile("" : "+f"(d[i])::"memory");
}
template <int N> __device__ __forceinline__ void reg_fence_u(uint32_t (&d)[N]) {
#pragma unroll
  for (int i = 0; i < N; i++) asm volatile("" : "+r"(d[i])::"memory");
}
template <int N> __device__ __forceinline__ void reg_def(float (&d)[N]) {
#pragma unroll
  for (int i = 0; i < N; i++) d[i] = 0.f;
}

__device__ __forceinline__ void wgmma_n192_ss_bt(float (&d)[96], uint64_t da, uint64_t db, int sc) {
  asm volatile("{\n.reg .pred p;\nsetp.ne.b32 p, %98, 0;\n"
    "wgmma.mma_async.sync.aligned.m64n192k16.f32.bf16.bf16 "
    "{%0, %1, %2, %3, %4, %5, %6, %7, %8, %9, %10, %11, %12, %13, %14, %15, "
    "%16, %17, %18, %19, %20, %21, %22, %23, %24, %25, %26, %27, %28, %29, %30, %31, "
    "%32, %33, %34, %35, %36, %37, %38, %39, %40, %41, %42, %43, %44, %45, %46, %47, "
    "%48, %49, %50, %51, %52, %53, %54, %55, %56, %57, %58, %59, %60, %61, %62, %63, "
    "%64, %65, %66, %67, %68, %69, %70, %71, %72, %73, %74, %75, %76, %77, %78, %79, "
    "%80, %81, %82, %83, %84, %85, %86, %87, %88, %89, %90, %91, %92, %93, %94, %95}, "
    "%96, %97, p, 1, 1, 0, 1;\n}\n"
    : "+f"(d[0]), "+f"(d[1]), "+f"(d[2]), "+f"(d[3]), "+f"(d[4]), "+f"(d[5]), "+f"(d[6]), "+f"(d[7]),
      "+f"(d[8]), "+f"(d[9]), "+f"(d[10]), "+f"(d[11]), "+f"(d[12]), "+f"(d[13]), "+f"(d[14]), "+f"(d[15]),
      "+f"(d[16]), "+f"(d[17]), "+f"(d[18]), "+f"(d[19]), "+f"(d[20]), "+f"(d[21]), "+f"(d[22]), "+f"(d[23]),
      "+f"(d[24]), "+f"(d[25]), "+f"(d[26]), "+f"(d[27]), "+f"(d[28]), "+f"(d[29]), "+f"(d[30]), "+f"(d[31]),
      "+f"(d[32]), "+f"(d[33]), "+f"(d[34]), "+f"(d[35]), "+f"(d[36]), "+f"(d[37]), "+f"(d[38]), "+f"(d[39]),
      "+f"(d[40]), "+f"(d[41]), "+f"(d[42]), "+f"(d[43]), "+f"(d[44]), "+f"(d[45]), "+f"(d[46]), "+f"(d[47]),
      "+f"(d[48]), "+f"(d[49]), "+f"(d[50]), "+f"(d[51]), "+f"(d[52]), "+f"(d[53]), "+f"(d[54]), "+f"(d[55]),
      "+f"(d[56]), "+f"(d[57]), "+f"(d[58]), "+f"(d[59]), "+f"(d[60]), "+f"(d[61]), "+f"(d[62]), "+f"(d[63]),
      "+f"(d[64]), "+f"(d[65]), "+f"(d[66]), "+f"(d[67]), "+f"(d[68]), "+f"(d[69]), "+f"(d[70]), "+f"(d[71]),
      "+f"(d[72]), "+f"(d[73]), "+f"(d[74]), "+f"(d[75]), "+f"(d[76]), "+f"(d[77]), "+f"(d[78]), "+f"(d[79]),
      "+f"(d[80]), "+f"(d[81]), "+f"(d[82]), "+f"(d[83]), "+f"(d[84]), "+f"(d[85]), "+f"(d[86]), "+f"(d[87]),
      "+f"(d[88]), "+f"(d[89]), "+f"(d[90]), "+f"(d[91]), "+f"(d[92]), "+f"(d[93]), "+f"(d[94]), "+f"(d[95])
    : "l"(da), "l"(db), "r"(sc));
}

__device__ __forceinline__ void wgmma_n96_rs(float (&d)[48], uint32_t a0, uint32_t a1, uint32_t a2, uint32_t a3, uint64_t db, int sc) {
  asm volatile("{\n.reg .pred p;\nsetp.ne.b32 p, %53, 0;\n"
    "wgmma.mma_async.sync.aligned.m64n96k16.f32.bf16.bf16 "
    "{%0, %1, %2, %3, %4, %5, %6, %7, %8, %9, %10, %11, %12, %13, %14, %15, "
    "%16, %17, %18, %19, %20, %21, %22, %23, %24, %25, %26, %27, %28, %29, %30, %31, "
    "%32, %33, %34, %35, %36, %37, %38, %39, %40, %41, %42, %43, %44, %45, %46, %47}, "
    "{%48, %49, %50, %51}, %52, p, 1, 1, 0;\n}\n"
    : "+f"(d[0]), "+f"(d[1]), "+f"(d[2]), "+f"(d[3]), "+f"(d[4]), "+f"(d[5]), "+f"(d[6]), "+f"(d[7]),
      "+f"(d[8]), "+f"(d[9]), "+f"(d[10]), "+f"(d[11]), "+f"(d[12]), "+f"(d[13]), "+f"(d[14]), "+f"(d[15]),
      "+f"(d[16]), "+f"(d[17]), "+f"(d[18]), "+f"(d[19]), "+f"(d[20]), "+f"(d[21]), "+f"(d[22]), "+f"(d[23]),
      "+f"(d[24]), "+f"(d[25]), "+f"(d[26]), "+f"(d[27]), "+f"(d[28]), "+f"(d[29]), "+f"(d[30]), "+f"(d[31]),
      "+f"(d[32]), "+f"(d[33]), "+f"(d[34]), "+f"(d[35]), "+f"(d[36]), "+f"(d[37]), "+f"(d[38]), "+f"(d[39]),
      "+f"(d[40]), "+f"(d[41]), "+f"(d[42]), "+f"(d[43]), "+f"(d[44]), "+f"(d[45]), "+f"(d[46]), "+f"(d[47])
    : "r"(a0), "r"(a1), "r"(a2), "r"(a3), "l"(db), "r"(sc));
}

__device__ __forceinline__ void wgmma_n64_rs_bt(float (&d)[32], uint32_t a0, uint32_t a1, uint32_t a2, uint32_t a3, uint64_t db, int sc) {
  asm volatile("{\n.reg .pred p;\nsetp.ne.b32 p, %37, 0;\n"
    "wgmma.mma_async.sync.aligned.m64n64k16.f32.bf16.bf16 "
    "{%0, %1, %2, %3, %4, %5, %6, %7, %8, %9, %10, %11, %12, %13, %14, %15, "
    "%16, %17, %18, %19, %20, %21, %22, %23, %24, %25, %26, %27, %28, %29, %30, %31}, "
    "{%32, %33, %34, %35}, %36, p, 1, 1, 1;\n}\n"
    : "+f"(d[0]), "+f"(d[1]), "+f"(d[2]), "+f"(d[3]), "+f"(d[4]), "+f"(d[5]), "+f"(d[6]), "+f"(d[7]),
      "+f"(d[8]), "+f"(d[9]), "+f"(d[10]), "+f"(d[11]), "+f"(d[12]), "+f"(d[13]), "+f"(d[14]), "+f"(d[15]),
      "+f"(d[16]), "+f"(d[17]), "+f"(d[18]), "+f"(d[19]), "+f"(d[20]), "+f"(d[21]), "+f"(d[22]), "+f"(d[23]),
      "+f"(d[24]), "+f"(d[25]), "+f"(d[26]), "+f"(d[27]), "+f"(d[28]), "+f"(d[29]), "+f"(d[30]), "+f"(d[31])
    : "r"(a0), "r"(a1), "r"(a2), "r"(a3), "l"(db), "r"(sc));
}

__device__ __forceinline__ void wgmma_n32_rs_bt(float (&d)[16], uint32_t a0, uint32_t a1, uint32_t a2, uint32_t a3, uint64_t db, int sc) {
  asm volatile("{\n.reg .pred p;\nsetp.ne.b32 p, %21, 0;\n"
    "wgmma.mma_async.sync.aligned.m64n32k16.f32.bf16.bf16 "
    "{%0, %1, %2, %3, %4, %5, %6, %7, %8, %9, %10, %11, %12, %13, %14, %15}, "
    "{%16, %17, %18, %19}, %20, p, 1, 1, 1;\n}\n"
    : "+f"(d[0]), "+f"(d[1]), "+f"(d[2]), "+f"(d[3]), "+f"(d[4]), "+f"(d[5]), "+f"(d[6]), "+f"(d[7]),
      "+f"(d[8]), "+f"(d[9]), "+f"(d[10]), "+f"(d[11]), "+f"(d[12]), "+f"(d[13]), "+f"(d[14]), "+f"(d[15])
    : "r"(a0), "r"(a1), "r"(a2), "r"(a3), "l"(db), "r"(sc));
}

#define PF_START 2000
#define PF_SW 44
#define ZERO_START 27000
#define PF_LAG 0
#define PF_DEPTH 3
#define PF_DEPTH2 3

#define EXPECT() mbar_expect_tx(fullb + 8 * s, SLOT)
#define LD(x) x
#define EP 0
#define NEARLY 3
#define INIT_PACE 600

constexpr uint32_t HI_128 = (1024u >> 4) | (1u << 30);
constexpr uint32_t LBO_K = (1u << 16);
constexpr uint32_t LBO_WQ = ((2048u >> 4) << 16);

__device__ __forceinline__ void softmax24(float (&v)[24], uint32_t (&p)[12]) {
  float m0 = fmaxf(v[0], v[1]), m1 = fmaxf(v[2], v[3]);
#pragma unroll
  for (int t = 1; t < 6; t++) {
    m0 = fmaxf(m0, fmaxf(v[4 * t], v[4 * t + 1]));
    m1 = fmaxf(m1, fmaxf(v[4 * t + 2], v[4 * t + 3]));
  }
  m0 = fmaxf(m0, __shfl_xor_sync(0xffffffffu, m0, 1));
  m1 = fmaxf(m1, __shfl_xor_sync(0xffffffffu, m1, 1));
  m0 = fmaxf(m0, __shfl_xor_sync(0xffffffffu, m0, 2));
  m1 = fmaxf(m1, __shfl_xor_sync(0xffffffffu, m1, 2));
  const float cs = 0.07216878364870322f * 1.4426950408889634f;
  const float b0 = m0 * cs, b1 = m1 * cs;
  float s0 = 0.f, s1 = 0.f;
#pragma unroll
  for (int t = 0; t < 6; t++) {
    v[4 * t] = ex2(fmaf(v[4 * t], cs, -b0));
    v[4 * t + 1] = ex2(fmaf(v[4 * t + 1], cs, -b0));
    v[4 * t + 2] = ex2(fmaf(v[4 * t + 2], cs, -b1));
    v[4 * t + 3] = ex2(fmaf(v[4 * t + 3], cs, -b1));
    s0 += v[4 * t] + v[4 * t + 1];
    s1 += v[4 * t + 2] + v[4 * t + 3];
  }
  s0 += __shfl_xor_sync(0xffffffffu, s0, 1);
  s1 += __shfl_xor_sync(0xffffffffu, s1, 1);
  s0 += __shfl_xor_sync(0xffffffffu, s0, 2);
  s1 += __shfl_xor_sync(0xffffffffu, s1, 2);
  const float i0 = rcp(s0), i1 = rcp(s1);
#pragma unroll
  for (int t = 0; t < 6; t++) {
    p[2 * t] = pack_bf16(v[4 * t] * i0, v[4 * t + 1] * i0);
    p[2 * t + 1] = pack_bf16(v[4 * t + 2] * i1, v[4 * t + 3] * i1);
  }
}

template <int A, int B>
__device__ __forceinline__ int xor_range(const uint32_t (&o)[48]) {
  uint32_t x = o[A];
#pragma unroll
  for (int i = A + 1; i < B; i++) x ^= o[i];
  return (int)x;
}
template <int A, int B>
__device__ __forceinline__ uint32_t zero_after(const uint32_t (&o)[48], uint32_t warp_uniform) {
  uint32_t x = o[A];
#pragma unroll
  for (int i = A + 1; i < B; i++) x ^= o[i];
  return __shfl_sync(0xffffffffu, warp_uniform, (int)x) ^ warp_uniform;
}

template <int NW, int CL>
__global__ void __launch_bounds__((NW + 1) * 128, 1)
fused_kernel(const __grid_constant__ Params prm, __nv_bfloat16* __restrict__ out) {
  extern __shared__ uint8_t smem_raw[];
  const uint32_t sbase = (smem_u32(smem_raw) + 1023u) & ~1023u;
  const uint32_t fullb = sbase + NSLOT * SLOT;
  const uint32_t emptyb = fullb + 80;
  const uint32_t rfullb = fullb + 320;
  const uint32_t rfreeb = fullb + 368;
  const uint32_t zerob = fullb + 416;
  const uint32_t progb = fullb + 424;
  const uint32_t pvdb = fullb + 432;
  const uint32_t pfb = fullb + 448;

  const int warp = __shfl_sync(0xffffffffu, threadIdx.x >> 5, 0);
  const int lane = threadIdx.x & 31;
  const uint32_t crank = blockIdx.x & (CL - 1);
  const uint32_t rank = crank & 1;
  const int rg = NW == 3 ? (blockIdx.x >> 1) & 3 : blockIdx.x >> 1;
  int grp = NW == 2 ? 15 : CL == 8 ? blockIdx.x >> 3 : 16 - (gridDim.x >> 3) + (blockIdx.x >> 3);
  if (CL == 8 && gridDim.x == 120) {
    const int c = blockIdx.x >> 3;
    const int G = c < 8 ? c : c - 7, second = c < 8 ? 0 : 1;
    const int pp = (G == 0 || (G >= 4 && G <= 6)) ? 1 : 0;
    const int gi = (G == 0 || G == 7) ? 3 : (G <= 3 ? G - 1 : G - 4);
    grp = pp * 8 + gi * 2 + second;
  }
  const int p = grp >> 3;
  const int h0 = (grp & 7) * 2 + rank;
  const int row0 = rg * (NW * 64);
  const int b0 = row0 / 48;
  const int cta = NW == 3 ? (grp * 4 + rg) * 2 + rank : (blockIdx.x < 8 ? grp * 8 : 120) + blockIdx.x;
  const uint32_t t_start = clk32();
  asm volatile("griddepcontrol.launch_dependents;" ::: "memory");

  if (warp >= 4 * NW) {
    if (NW == 3) asm volatile("setmaxnreg.dec.sync.aligned.u32 32;");
    if (threadIdx.x == NW * 128) {
      STAMP(0); GSTAMP(62);
      const CUtensorMap* mx = &prm.x[p];
      const CUtensorMap* mwq = &prm.wq[p];
#pragma unroll
      for (int i = 0; i < 2 * NEARLY; i++) mbar_init(fullb + 8 * i, 1);
      asm volatile("fence.proxy.async.shared::cta;" ::: "memory");
#pragma unroll
      for (int kb = 0; kb < NEARLY; kb++) {
        const int s = 2 * kb;
        EXPECT();
        LD(tma2d(sbase + s * SLOT, mx, fullb + 8 * s, kb * 64, row0));
        LD(tma2d(sbase + s * SLOT + 12288, mx, fullb + 8 * s, kb * 64, row0 + 96));
        {
          const int s = 2 * kb + 1;
          EXPECT();
#pragma unroll
          for (int i = 0; i < 4; i++)
            LD(tma3d(sbase + s * SLOT + i * 6144, mwq, fullb + 8 * s, 0, kb * 64 + i * 16, h0 * 3));
        }
      }
      STAMP(47);
#pragma unroll
      for (int i = 0; i < NSLOT; i++) {
        if (i >= 2 * NEARLY) mbar_init(fullb + 8 * i, 1);
        mbar_init(emptyb + 8 * i, 2 * NW); mbar_init(emptyb + 80 + 8 * i, CL == 8 ? 4 * NW : NW); mbar_init(emptyb + 160 + 8 * i, NW);
      }
#pragma unroll
      for (int i = 0; i < 6; i++) { mbar_init(rfullb + 8 * i, 1); mbar_init(rfreeb + 8 * i, 4); }
      mbar_init(zerob, 1);
      mbar_init(pvdb, NW);
#pragma unroll
      for (int i = 0; i < 8; i++) mbar_init(pfb + 8 * i, 1);
      asm volatile("st.shared.u32 [%0], %1;" ::"r"(progb), "r"(9) : "memory");
      asm volatile("fence.mbarrier_init.release.cluster;" ::: "memory");
      asm volatile("fence.proxy.async.shared::cta;" ::: "memory");
      pf_map(&prm.k[p]); pf_map(&prm.v[p]); pf_map(&prm.wo[p]); pf_map(&prm.out);
      STAMP(40);
    }
    __syncwarp();
    asm volatile("barrier.cluster.arrive.relaxed.aligned;" ::: "memory");
    asm volatile("barrier.cluster.wait.acquire.aligned;" ::: "memory");
    if (warp == 4 * NW) {
      if (lane == 0) {
        STAMP(41);
        const CUtensorMap* mx = &prm.x[p];
        const CUtensorMap* mwq = &prm.wq[p];
        const CUtensorMap* mk = &prm.k[p];
        const CUtensorMap* mv = &prm.v[p];
        const CUtensorMap* mwo = &prm.wo[p];
        const int xrow = row0 + rank * 96;
        const uint32_t roff = rank * 12288;
        const uint16_t xmask = (uint16_t)(3u << (crank & 6u));
        const uint16_t wmask = (uint16_t)(0x55u << rank);
        int s = 2 * NEARLY - 1, t = 2 * NEARLY;
        uint32_t tn = clk32();
        uint32_t ph = 0;
#define ACQ(kind) do { s = t <= 49 ? NEXT9(s) : NEXT7(s); \
          if (t >= 9) { mbar_wait(emptyb + 80 * (kind) + 8 * s, (ph >> (9 * (kind) + s)) & 1u); ph ^= 1u << (9 * (kind) + s); } \
          t++; asm volatile("st.volatile.shared.u32 [%0], %1;" ::"r"(progb), "r"(t) : "memory"); EXPECT(); } while (0)
#pragma unroll 1
        for (int u = 0; u < 2; u++) {
          const int h = h0 + 16 * u;
#pragma unroll 1
          for (int kb = u ? 0 : NEARLY; kb < 10; kb++) {
            if (t < 9) { while ((int)(clk32() - tn) < 0) { } tn += INIT_PACE; }
            ACQ(0);
            LD(tma2d_mc(sbase + s * SLOT + roff, mx, fullb + 8 * s, kb * 64, xrow, xmask));
            ACQ(1);
            if (CL == 8) {
              LD(tma3d_mc(sbase + s * SLOT + rg * 6144, mwq, fullb + 8 * s, 0, kb * 64 + rg * 16, h * 3, wmask));
            } else {
#pragma unroll
              for (int i = 0; i < 4; i++)
                LD(tma3d(sbase + s * SLOT + i * 6144, mwq, fullb + 8 * s, 0, kb * 64 + i * 16, h * 3));
            }
          }
#pragma unroll 1
          for (int c = 0; c < 3 + 3 * u; c++) {
            ACQ(2);
            LD(tma4d(sbase + s * SLOT, c < 3 ? mk : mv, fullb + 8 * s, (c < 3 ? c : c - 3) * 64, 0, c < 3 ? h : h0, b0));
          }
          STAMP(1 + u);
        }
#pragma unroll 1
        while (t < 72) {
          int r = t - 49;
          if (r >= 2 * KE && r < 2 * KE + 3) {
            ACQ(2);
            LD(tma4d(sbase + s * SLOT, mv, fullb + 8 * s, (r - 2 * KE) * 64, 0, h0 + 16, b0));
          } else {
            int cj, f, hd;
            if (r < 2 * KE) { cj = 0; f = r; hd = 0; }
            else if (r < 4 * KE + 3) { cj = 0; f = r - (2 * KE + 3); hd = 1; }
            else { r -= 3; cj = r >> 2; f = (r >> 1) & 1; hd = r & 1; }
            const int col = (cj + (f == (int)rank ? 5 : 0)) * 64;
            const int row = (h0 + 16 * hd) * 192;
            ACQ(1);
            if (CL == 8) {
              LD(tma2d_mc(sbase + s * SLOT + rg * 6144, mwo, fullb + 8 * s, col, row + rg * 48, wmask));
            } else {
#pragma unroll
              for (int i = 0; i < 4; i++)
                LD(tma2d(sbase + s * SLOT + i * 6144, mwo, fullb + 8 * s, col, row + i * 48));
            }
          }
        }
        STAMP(5);
      }
    } else if (warp == 4 * NW + 3) {
      while ((int)(clk32() - t_start) < ZERO_START) __nanosleep(200);
      unsigned base;
      if (rg < 4) {
        const int reg = p * 4 + rg;
        for (;;) {
          unsigned old = 0;
          if (lane == 0) old = atomicAdd(&g_claim[reg * 32], 1u);
          old = __shfl_sync(0xffffffffu, old, 0);
          base = old & ~31u;
          if ((old & 31u) >= 16u) break;
          uint4* dz = reinterpret_cast<uint4*>(out) + (size_t)(rg * 192 + (old & 31u) * 12) * 160 + p * 80;
#pragma unroll 1
          for (int i = lane; i < 960; i += 32) dz[(i / 80) * 160 + i % 80] = make_uint4(0, 0, 0, 0);
          asm volatile("fence.proxy.async;" ::: "memory");
          __syncwarp();
          if (lane == 0) asm volatile("red.release.gpu.global.add.u32 [%0], 2;" ::"l"(&g_done[reg * 32]) : "memory");
        }
      } else {
        unsigned old = 0;
        if (lane == 0) old = atomicAdd(&g_claim[8 * 32], 8u);
        base = __shfl_sync(0xffffffffu, old, 0) & ~31u;
      }
      if (lane == 0) {
#pragma unroll 1
        for (int r = row0 / 192; r <= (row0 + NW * 64 - 1) / 192; r++) {
          while (ld_acquire(&g_done[(p * 4 + r) * 32]) - base < 32u) {
            if (EXPIRED()) break;
            __nanosleep(200);
          }
        }
        asm volatile("fence.proxy.async;" ::: "memory");
        mbar_arrive_local(zerob);
        STAMP(7);
      }
      __syncwarp();
    }
    else if (threadIdx.x == NW * 128 + 32) {
      const size_t kvo = (size_t)(b0 * 32 + h0) * 18432;
      while ((int)(clk32() - t_start) < PF_START) __nanosleep(50);
      uint32_t ph = 0;
      int s = 0, n = 0;
#pragma unroll 1
      for (int seg = 0; seg < 4; seg++) {
        const uint8_t* a = (seg < 2 ? prm.kp[p] : prm.vp[p]) + kvo + (seg & 1) * (16 * 18432);
        const int tile = seg == 0 ? 20 : seg == 3 ? 49 + 2 * KE : 40 + 3 * seg;
#pragma unroll 1
        for (int i = 0; i < 12 && b0 + i / 3 < 16; i++) {
          int pr;
          for (;;) {
            asm volatile("ld.volatile.shared.u32 %0, [%1];" : "=r"(pr) : "r"(progb) : "memory");
            const int w = pr > PF_SW ? PF_DEPTH2 : PF_DEPTH;
            if (n >= w) {
              const int o = (s - n) & 7;
              mbar_wait(pfb + 8 * o, (ph >> o) & 1u); ph ^= 1u << o; n--;
              continue;
            }
            const int t1 = pr - PF_LAG, t0 = t1 - 1;
            if (PF_LAG == 0 || pr > PF_SW || t0 < 0) break;
            if (mbar_test(fullb + 8 * (t1 % 9), (t1 / 9) & 1) && mbar_test(fullb + 8 * (t0 % 9), (t0 / 9) & 1)) break;
            if (EXPIRED()) break;
            __nanosleep(40);
          }
          if (pr > tile) break;
          n++;
          mbar_expect_tx(pfb + 8 * s, 6144);
          asm volatile("cp.async.bulk.shared::cluster.global.mbarrier::complete_tx::bytes [%0], [%1], %2, [%3];"
                       ::"r"(fullb + 1024), "l"(a + (i / 3) * (32 * 18432) + (i % 3) * 6144), "r"(6144), "r"(pfb + 8 * s) : "memory");
          s = (s + 1) & 7;
        }
        STAMP(seg == 0 ? 33 : 34 + seg);
      }
      while (n > 0) { const int w = (s - n) & 7; mbar_wait(pfb + 8 * w, (ph >> w) & 1u); ph ^= 1u << w; n--; }
    }
  } else {
    if (NW == 3) asm volatile("setmaxnreg.inc.sync.aligned.u32 160;");
    const int wg = warp >> 2;
    const int wl = warp & 3;
    asm volatile("barrier.cluster.arrive.relaxed.aligned;" ::: "memory");
    asm volatile("barrier.cluster.wait.acquire.aligned;" ::: "memory");
    if (threadIdx.x == 0) STAMP(43);
    const uint32_t relx = mapa(emptyb, (crank & 6u) | (wl & 1));
    const uint32_t relw = mapa(emptyb + 80, CL == 8 ? (uint32_t)(wl * 2) + rank : crank);
    const uint32_t rell = mapa(emptyb + 160, crank);
    const uint32_t peer = mapa(sbase, crank ^ 1);
    const uint32_t sdesc = (sbase & 0x3FFFFu) >> 4;
    const int wrow = row0 + wg * 64;
    const int wb = wrow / 48;
    const uint32_t kvd = sdesc + (wb - b0) * (6144 >> 4);
    const bool hb = wl * 16 + wrow - wb * 48 >= 48;
    int ns = 0;
    uint64_t nkq;
    uint32_t phm = 0;
#define SL(X) ((X) & 15)
#define WAITN(X, NEXT) do { X = ns | ((int)nkq & 3) << 4; nkq >>= 2; \
      mbar_wait(fullb + 8 * ns, (phm >> ns) & 1u); phm ^= 1u << ns; ns = NEXT(ns); } while (0)
#define WAITF(X) WAITN(X, NEXT9)
#define RELN(X, n) do { const int nk_ = (X) >> 4; \
      const uint32_t ra_ = nk_ == 0 ? relx : (nk_ == 1 ? relw : rell); \
      const int nw_ = nk_ == 0 ? 2 : (nk_ == 1 ? (CL == 8 ? 4 : 1) : (nk_ == 2 ? 1 : 0)); \
      if (lane == 0 && wl < nw_) mbar_arrive_cluster_n(ra_ + 8 * SL(X), n); } while (0)
#define REL(X) RELN(X, 1)
#define TOK_WAIT() asm volatile("bar.sync %0, 256;" ::"r"(1 + wg) : "memory")
#define TOK_PASS() asm volatile("bar.arrive %0, 256;" ::"r"(wg == NW - 1 ? 1 : 2 + wg) : "memory")
    if (wg == NW - 1) TOK_PASS();

    uint32_t p0[12], p1[12];
    {
      float v[24];
      reg_def(v);
#pragma unroll 1
      for (int u = 0; u < 2; u++) {
        uint32_t qf[48];
        nkq = u ? NK_B : NK_A;
        {
          float acc[96];
          reg_def(acc);
          int sa, sb, pa, pb;
#define QK_ISSUE(kb, first) do { \
            FST(16 * u + kb, 0); WAITF(sa); FST(16 * u + kb, 1); WAITF(sb); FST(16 * u + kb, 2); \
            const uint32_t alo = (sdesc + SL(sa) * (SLOT >> 4) + wg * (8192 >> 4)) | LBO_K; \
            const uint32_t blo = (sdesc + SL(sb) * (SLOT >> 4)) | LBO_WQ; \
            wg_fence(); \
            _Pragma("unroll") \
            for (int k = 0; k < 4; k++) \
              wgmma_n192_ss_bt(acc, mk_desc(alo + k * 2, HI_128), mk_desc(blo + k * (6144 >> 4), HI_128), !(first) || k != 0); \
            wg_commit(); } while (0)
          QK_ISSUE(0, true);
          if (threadIdx.x == 0) STAMP(48 + u);
          pa = sa; pb = sb;
          if (u) softmax24(v, p0);
#pragma unroll 1
          for (int kb = 1; kb < 10; kb++) {
            QK_ISSUE(kb, false);
            wg_wait<1>();
            REL(pa); REL(pb);
            pa = sa; pb = sb;
          }
          wg_wait<0>();
          reg_fence(acc);
          REL(pa); REL(pb);
          if (threadIdx.x == 0) STAMP(8 + 2 * u);
#pragma unroll
          for (int i = 0; i < 48; i++) qf[i] = pack_bf16(acc[2 * i], acc[2 * i + 1]);
        }
        float sc[48];
        reg_def(sc);
        int ks[3];
        WAITF(ks[0]);
        FST(16 * u + 10, 0);
        TOK_WAIT();
        FST(16 * u + 10, 1);
        wg_fence();
#pragma unroll
        for (int c = 0; c < 3; c++) {
          if (c) WAITF(ks[c]);
          const uint32_t blo = (kvd + SL(ks[c]) * (SLOT >> 4)) | LBO_K;
#pragma unroll
          for (int k = 0; k < 4; k++) {
            const int f = (c * 4 + k) * 4;
            if (c * 4 + k == 12 - EP) TOK_PASS();
            wgmma_n96_rs(sc, qf[f], qf[f + 1], qf[f + 2], qf[f + 3], mk_desc(blo + k * 2, HI_128), (c | k) != 0);
          }
        }
        wg_commit();
        if (EP == 0) TOK_PASS();
        FST(16 * u + 10, 2);
        wg_wait<0>();
        reg_fence(sc);
        FST(16 * u + 10, 3);
        REL(ks[0]); REL(ks[1]); REL(ks[2]);
        if (threadIdx.x == 0) STAMP(9 + 2 * u);
#pragma unroll
        for (int i = 0; i < 24; i++) v[i] = hb ? sc[24 + i] : sc[i];
      }
      softmax24(v, p1);
    }
    nkq = NK_C;
    const uint32_t hbm = (int)((threadIdx.x >> 5) & 3) * 16 + wrow - wb * 48 >= 48 ? 0xffffffffu : 0u;
#define PV_MASKS(P, dep) \
      uint32_t e[24]; \
      { const uint32_t m = __shfl_sync(0xffffffffu, hbm, dep);        \
        _Pragma("unroll") \
        for (int i = 0; i < 12; i++) { e[i] = P[i] & ~m; e[12 + i] = P[i] & m; } } \
      reg_fence_u(e)
#define PV_PIECE(A, X, LAST) do { \
      const uint32_t blo = (kvd + SL(X) * (SLOT >> 4)) | LBO_K; \
      _Pragma("unroll") \
      for (int kk = 0; kk < 6; kk++) { \
        if (LAST && kk == 6 - EP) TOK_PASS(); \
        wgmma_n64_rs_bt(A, e[4 * kk], e[4 * kk + 1], e[4 * kk + 2], e[4 * kk + 3], mk_desc(blo + kk * 128, HI_128), kk != 0); \
      } } while (0)
#define PV_PACK(O, c, A) do { \
      _Pragma("unroll") \
      for (int i = 0; i < 16; i++) O[16 * (c) + i] = pack_bf16v(A[2 * i], A[2 * i + 1]); } while (0)
#define ZERO_AFTER(O, a, b) zero_after<a, b>(O, hbm)
    uint32_t zz = 0;
    uint32_t o0[48], o1[48];
    float acc[32];
    {
      PV_MASKS(p0, (int)p1[0]);
      float a0[32], a1[32];
      reg_def(a0); reg_def(a1); reg_def(acc);
      int v0, v1, v2;
      WAITF(v0);
      FST(11, 0);
      TOK_WAIT();
      FST(11, 1);
      wg_fence();
      PV_PIECE(a0, v0, false);
      WAITF(v1);
      PV_PIECE(a1, v1, false);
      WAITF(v2);
      PV_PIECE(acc, v2, true);
      wg_commit();
      if (EP == 0) TOK_PASS();
      FST(11, 2);
      wg_wait<0>();
      reg_fence(a0); reg_fence(a1); reg_fence(acc);
      FST(11, 3);
      REL(v2);
      if (lane == 0 && wl == 1) mbar_arrive_local(pvdb);
      PV_PACK(o0, 0, a0); PV_PACK(o0, 1, a1); PV_PACK(o0, 2, acc);
    }
    if (threadIdx.x == 0) STAMP(12);
#undef WAITF
#define WAITF(X) WAITN(X, NEXT7)

    const uint32_t woff = SLOT + wg * 8192 + wl * 2048;
    const uint32_t pbar = peer + (NSLOT * SLOT) + 320 + wg * 8;
#define ROUND(r, UA, UB, MID) do { \
      int sw = 0, sx = 0; \
      WAITF(sw); \
      FST(32 + r, 0); \
      const uint32_t blo = (sdesc + SL(sw) * (SLOT >> 4)) | LBO_K; \
      TOK_WAIT(); \
      FST(32 + r, 1); \
      wg_fence(); \
      _Pragma("unroll") \
      for (int kk = 0; kk < 12; kk++) { \
        if (!(UA && UB) && kk == 12 - EP) TOK_PASS(); \
        if (UA) wgmma_n64_rs_bt(acc, o0[4 * kk], o0[4 * kk + 1], o0[4 * kk + 2], o0[4 * kk + 3], mk_desc(blo + kk * 128, HI_128), kk != 0); \
        else wgmma_n64_rs_bt(acc, o1[4 * kk], o1[4 * kk + 1], o1[4 * kk + 2], o1[4 * kk + 3], mk_desc(blo + kk * 128, HI_128), 1); \
      } \
      if (UA && UB) { \
        WAITF(sx); \
        const uint32_t bl2 = (sdesc + SL(sx) * (SLOT >> 4)) | LBO_K; \
        _Pragma("unroll") \
        for (int kk = 0; kk < 12; kk++) { \
          if (kk == 12 - EP) TOK_PASS(); \
          wgmma_n64_rs_bt(acc, o1[4 * kk], o1[4 * kk + 1], o1[4 * kk + 2], o1[4 * kk + 3], mk_desc(bl2 + kk * 128, HI_128), 1); \
        } \
      } \
      wg_commit(); \
      if (EP == 0) TOK_PASS(); \
      FST(32 + r, 2); \
      MID; \
      wg_wait<0>(); \
      reg_fence(acc); \
      FST(32 + r, 3); \
      REL(sw); \
      if (UA && UB) REL(sx); } while (0)
#define FLUSH(j) do { \
      asm volatile("fence.proxy.async.shared::cta;" ::: "memory"); \
      __syncwarp(); \
      if (lane == 0) { \
        if ((j) == 0) mbar_wait(zerob, 0); \
        tma_red_add(&prm.out, sbase + woff + ((j) & 1) * SLOT, p * 640 + ((j) + rank * 5) * 64, wrow + wl * 16); \
        asm volatile("cp.async.bulk.commit_group;" ::: "memory"); \
      } \
      __syncwarp(); } while (0)
#define OFFER(k) do { \
      if (lane == 0) { \
        if (wl == 0) mbar_expect_tx(rfullb + 8 * (3 * (k) + wg), 8192); \
        mbar_arrive_cluster(pbar + 48 + 24 * (k)); \
      } } while (0)
#define HANDBACK(j) do { \
      if (lane == 0) asm volatile("cp.async.bulk.wait_group.read 0;" ::: "memory"); \
      OFFER((j) & 1); \
      __syncwarp(); } while (0)
#define LOAD_ADD(wb_, OP) do { \
      _Pragma("unroll") \
      for (int i = 0; i < 4; i++) { \
        uint32_t w0, w1, w2, w3; \
        asm volatile("ld.shared.v4.b32 {%0, %1, %2, %3}, [%4];" : "=r"(w0), "=r"(w1), "=r"(w2), "=r"(w3) : "r"((wb_) + lane * 16 + i * 512) : "memory"); \
        acc[8 * i + 0] OP __uint_as_float(w0 << 16); acc[8 * i + 1] OP __uint_as_float(w0 & 0xffff0000u); \
        acc[8 * i + 2] OP __uint_as_float(w1 << 16); acc[8 * i + 3] OP __uint_as_float(w1 & 0xffff0000u); \
        acc[8 * i + 4] OP __uint_as_float(w2 << 16); acc[8 * i + 5] OP __uint_as_float(w2 & 0xffff0000u); \
        acc[8 * i + 6] OP __uint_as_float(w3 << 16); acc[8 * i + 7] OP __uint_as_float(w3 & 0xffff0000u); \
      } \
      __syncwarp(); } while (0)
#define PAIR(j, UA, UB, DOF, DOH) do { \
      const uint32_t kb = (j) & 1, par = ((j) >> 1) & 1; \
      if (UA) reg_def(acc); else { LOAD_ADD(sbase + woff + zz, =); OFFER(0); } \
      ROUND(2 + 2 * (j), UA, UB, if (DOF) FLUSH((j) - 1)); \
      { \
        mbar_wait(rfreeb + 8 * (3 * kb + wg), par); \
        FST(34 + 2 * (j), 5); \
        const uint32_t da = peer + woff + lane * 16 + kb * SLOT; \
        _Pragma("unroll") \
        for (int i = 0; i < 4; i++) \
          st_async4(da + i * 512, pack_bf16(acc[8 * i], acc[8 * i + 1]), pack_bf16(acc[8 * i + 2], acc[8 * i + 3]), \
                    pack_bf16(acc[8 * i + 4], acc[8 * i + 5]), pack_bf16(acc[8 * i + 6], acc[8 * i + 7]), pbar + 24 * kb); \
        FST(34 + 2 * (j), 6); \
      } \
      if (UA) reg_def(acc); else { LOAD_ADD(sbase + woff + SLOT, =); OFFER(1); } \
      ROUND(3 + 2 * (j), UA, UB, if (DOH) HANDBACK((j) - 1)); \
      { \
        mbar_wait(rfullb + 8 * (3 * kb + wg), par); \
        FST(35 + 2 * (j), 4); \
        const uint32_t wb_ = sbase + woff + kb * SLOT; \
        LOAD_ADD(wb_, +=); \
        const int rr = lane & 15; \
        _Pragma("unroll") \
        for (int t = 0; t < 8; t += 2) \
          stsm4(wb_ + rr * 128 + (((t + (lane >> 4)) ^ (rr & 7)) << 4), pack_bf16(acc[4 * t], acc[4 * t + 1]), \
                pack_bf16(acc[4 * t + 2], acc[4 * t + 3]), pack_bf16(acc[4 * t + 4], acc[4 * t + 5]), \
                pack_bf16(acc[4 * t + 6], acc[4 * t + 7])); \
        FST(35 + 2 * (j), 6); \
      } } while (0)

    if (KE) {
#pragma unroll 1
      for (int f = 0; f < 2; f++) {
        reg_def(acc);
        ROUND(f, true, false, );
        if (f == 0) mbar_wait(pvdb, 0);
#pragma unroll
        for (int i = 0; i < 4; i++)
          asm volatile("st.shared.v4.b32 [%0], {%1, %2, %3, %4};" ::"r"(sbase + woff + f * SLOT + lane * 16 + i * 512),
                       "r"(pack_bf16(acc[8 * i], acc[8 * i + 1])), "r"(pack_bf16(acc[8 * i + 2], acc[8 * i + 3])),
                       "r"(pack_bf16(acc[8 * i + 4], acc[8 * i + 5])), "r"(pack_bf16(acc[8 * i + 6], acc[8 * i + 7])) : "memory");
      }
    }
#define PV_ONE(c) do { \
      PV_MASKS(p1, (int)__float_as_uint(acc[0])); \
      reg_def(acc); \
      int v0; \
      WAITF(v0); \
      FST(27 + c, 0); \
      TOK_WAIT(); \
      FST(27 + c, 1); \
      wg_fence(); \
      PV_PIECE(acc, v0, true); \
      wg_commit(); \
      if (EP == 0) TOK_PASS(); \
      FST(27 + c, 2); \
      if (!KE && c == 0) { mbar_wait(pvdb, 0); OFFER(0); OFFER(1); __syncwarp(); } \
      wg_wait<0>(); \
      reg_fence(acc); \
      FST(27 + c, 3); \
      REL(v0); \
      PV_PACK(o1, c, acc); } while (0)
    PV_ONE(0);
    PV_ONE(1);
    {
      uint32_t e[12];
      int v2;
      uint32_t m = __shfl_sync(0xffffffffu, hbm, (int)__float_as_uint(acc[0]));
#pragma unroll
      for (int i = 0; i < 12; i++) e[i] = p1[i] & ~m;
      reg_fence_u(e);
      reg_def(acc);
      WAITF(v2);
      const uint32_t blo = (kvd + SL(v2) * (SLOT >> 4)) | LBO_K;
      FST(29, 0);
      TOK_WAIT();
      FST(29, 1);
      wg_fence();
#pragma unroll
      for (int kk = 0; kk < 3; kk++) {
        if (kk == 3 - EP) TOK_PASS();
        wgmma_n64_rs_bt(acc, e[4 * kk], e[4 * kk + 1], e[4 * kk + 2], e[4 * kk + 3], mk_desc(blo + kk * 128, HI_128), kk != 0);
      }
      wg_commit();
      if (EP == 0) TOK_PASS();
      wg_wait<0>();
      reg_fence(acc);
      m = __shfl_sync(0xffffffffu, hbm, (int)__float_as_uint(acc[0]));
#pragma unroll
      for (int i = 0; i < 12; i++) e[i] = p1[i] & m;
      reg_fence_u(e);
      wg_fence();
#pragma unroll
      for (int kk = 0; kk < 3; kk++)
        wgmma_n64_rs_bt(acc, e[4 * kk], e[4 * kk + 1], e[4 * kk + 2], e[4 * kk + 3], mk_desc(blo + (kk + 3) * 128, HI_128), 1);
      wg_commit();
      wg_wait<0>();
      reg_fence(acc);
      FST(29, 3);
      REL(v2);
      PV_PACK(o1, 2, acc);
    }
    if (threadIdx.x == 0) STAMP(13);
    if (KE) PAIR(0, false, true, false, false);
#pragma unroll 1
    for (int j = KE; j < 5; j++) PAIR(j, true, true, j > 0, j > 0 && j < 4);
    FLUSH(4);
    if (threadIdx.x == 0) STAMP(24);
    if (lane == 0) asm volatile("cp.async.bulk.wait_group.read 0;" ::: "memory");
    if (threadIdx.x == (NW - 1) * 128) { STAMP(26); GSTAMP(63); }
  }
}

typedef CUresult (*EncFn)(CUtensorMap*, CUtensorMapDataType, cuuint32_t, void*, const cuuint64_t*, const cuuint64_t*,
                          const cuuint32_t*, const cuuint32_t*, CUtensorMapInterleave, CUtensorMapSwizzle,
                          CUtensorMapL2promotion, CUtensorMapFloatOOBfill);

bool encode(EncFn enc, CUtensorMap* m, void* ptr, int rank, const cuuint64_t* dims, const cuuint64_t* strides,
            const cuuint32_t* box, CUtensorMapSwizzle sw) {
  cuuint32_t es[5] = {1, 1, 1, 1, 1};
  return enc(m, CU_TENSOR_MAP_DATA_TYPE_BFLOAT16, rank, ptr, dims, strides, box, es, CU_TENSOR_MAP_INTERLEAVE_NONE, sw,
             CU_TENSOR_MAP_L2_PROMOTION_L2_128B, CU_TENSOR_MAP_FLOAT_OOB_FILL_NONE) == CUDA_SUCCESS;
}

}

extern "C" void kernel_launch(void* const* d_in, const int* in_sizes, int n_in, void* d_out, int out_size) {
  static EncFn enc = nullptr;
  static int n8 = 0;
  static bool narrow = false;
  cudaLaunchConfig_t cfg = {};
  cudaLaunchAttribute at[2];
  cfg.dynamicSmemBytes = SMEM_BYTES;
  cfg.stream = cudaStreamPerThread;
  at[0].id = cudaLaunchAttributeClusterDimension;
  at[0].val.clusterDim.y = 1;
  at[0].val.clusterDim.z = 1;
  at[1].id = cudaLaunchAttributeProgrammaticStreamSerialization;
  at[1].val.programmaticStreamSerializationAllowed = 1;
  cfg.attrs = at;
  if (!enc) {
    cudaDriverEntryPointQueryResult qr;
    void* fn = nullptr;
    if (cudaGetDriverEntryPoint("cuTensorMapEncodeTiled", &fn, cudaEnableDefault, &qr) != cudaSuccess || !fn) return;
    if (cudaFuncSetAttribute(fused_kernel<3, 8>, cudaFuncAttributeMaxDynamicSharedMemorySize, SMEM_BYTES) != cudaSuccess) return;
    if (cudaFuncSetAttribute(fused_kernel<3, 2>, cudaFuncAttributeMaxDynamicSharedMemorySize, SMEM_BYTES) != cudaSuccess) return;
    if (cudaFuncSetAttribute(fused_kernel<2, 2>, cudaFuncAttributeMaxDynamicSharedMemorySize, SMEM_BYTES) != cudaSuccess) return;
    int dev = 0, sms = 0;
    cudaGetDevice(&dev);
    cudaDeviceGetAttribute(&sms, cudaDevAttrMultiProcessorCount, dev);
    cfg.gridDim = dim3(128);
    cfg.blockDim = dim3(512);
    cfg.numAttrs = 1;
    at[0].val.clusterDim.x = 8;
    if (cudaOccupancyMaxActiveClusters(&n8, fused_kernel<3, 8>, &cfg) != cudaSuccess) { n8 = 0; (void)cudaGetLastError(); }
    if (n8 > 16) n8 = 16;
    narrow = n8 == 15 && sms >= 132;
    enc = (EncFn)fn;
  }
  Params prm;
  bool ok = true;
  for (int p = 0; p < 2; p++) {
    void* x = d_in[5 * p + 0];
    void* kc = d_in[5 * p + 1];
    void* vc = d_in[5 * p + 2];
    void* wq = d_in[5 * p + 3];
    void* wo = d_in[5 * p + 4];
    prm.kp[p] = (const uint8_t*)kc; prm.vp[p] = (const uint8_t*)vc;
    {
      cuuint64_t d[2] = {640, 768}, st[1] = {1280};
      cuuint32_t b[2] = {64, 96};
      ok &= encode(enc, &prm.x[p], x, 2, d, st, b, CU_TENSOR_MAP_SWIZZLE_128B);
    }
    {
      cuuint64_t d[3] = {64, 640, 96}, st[2] = {12288, 128};
      cuuint32_t b[3] = {64, 16, 3};
      ok &= encode(enc, &prm.wq[p], wq, 3, d, st, b, CU_TENSOR_MAP_SWIZZLE_128B);
    }
    {
      cuuint64_t d[4] = {192, 48, 32, 16}, st[3] = {384, 18432, 589824};
      cuuint32_t b[4] = {64, 48, 1, 4};
      ok &= encode(enc, &prm.k[p], kc, 4, d, st, b, CU_TENSOR_MAP_SWIZZLE_128B);
      ok &= encode(enc, &prm.v[p], vc, 4, d, st, b, CU_TENSOR_MAP_SWIZZLE_128B);
    }
    {
      cuuint64_t d[2] = {640, 6144}, st[1] = {1280};
      cuuint32_t b[2] = {64, 48};
      ok &= encode(enc, &prm.wo[p], wo, 2, d, st, b, CU_TENSOR_MAP_SWIZZLE_128B);
    }
  }
  {
    cuuint64_t d[2] = {1280, 768}, st[1] = {2560};
    cuuint32_t b[2] = {64, 16};
    ok &= encode(enc, &prm.out, d_out, 2, d, st, b, CU_TENSOR_MAP_SWIZZLE_128B);
  }
  if (!ok) return;
  if (n8 > 0) {
    cfg.gridDim = dim3(8 * n8);
    cfg.blockDim = dim3(512);
    cfg.numAttrs = 1;
    at[0].val.clusterDim.x = 8;
    cudaLaunchKernelEx(&cfg, fused_kernel<3, 8>, prm, (__nv_bfloat16*)d_out);
  }
  if (n8 < 16) {
    cfg.numAttrs = n8 > 0 ? 2 : 1;
    at[0].val.clusterDim.x = 2;
    if (narrow) {
      cfg.gridDim = dim3(12);
      cfg.blockDim = dim3(384);
      cudaLaunchKernelEx(&cfg, fused_kernel<2, 2>, prm, (__nv_bfloat16*)d_out);
    } else {
      cfg.gridDim = dim3(8 * (16 - n8));
      cfg.blockDim = dim3(512);
      cudaLaunchKernelEx(&cfg, fused_kernel<3, 2>, prm, (__nv_bfloat16*)d_out);
    }
  }
}
```
